```python
import torch

def _softmax(x, axis=-1):
    return torch.softmax(x, dim=axis)
def _gelu(x):
    return torch.nn.functional.gelu(x, approximate="tanh")
def _silu(x):
    return torch.nn.functional.silu(x)
def _sigmoid(x):
    return torch.sigmoid(x)
def _layernorm(x, axis=-1, eps=1e-5):
    m = x.mean(dim=axis, keepdim=True)
    v = x.var(dim=axis, keepdim=True, unbiased=False)
    return (x - m) / torch.sqrt(v + eps)
def _scatter_add(tgt, idx, src, axis=0):
    return tgt.clone().index_add_(axis, idx, src)
def _segment_sum(src, seg, n):
    out = torch.zeros((n,) + src.shape[1:], dtype=src.dtype)
    return out.index_add_(0, seg, src)
def _pad(x, pw):
    flat = tuple(v for pair in reversed(pw) for v in pair)
    return torch.nn.functional.pad(x, flat)

kernel_name = 'standalone__gqa_softmax__prompt'

def setup_inputs():

    _w = (lambda a: (lambda t: t.to(torch.bfloat16) if t.is_floating_point() else t)(torch.as_tensor(a)))
    B, Hq, Hkv, Sq, Sk, D = 1, 32, 32, 2048, 2048, 192
    return {
        "q": _w((lambda *s: torch.randn(*s, dtype=torch.bfloat16) * 0.8)(B, Hq, Sq, D)),
        "k": _w((lambda *s: torch.randn(*s, dtype=torch.bfloat16) * 0.8)(B, Hkv, Sk, D)),
        "v": _w((lambda *s: torch.randn(*s, dtype=torch.bfloat16) * 0.05)(B, Hkv, Sk, D)),
    }

def reference(q, k, v):
    B, Hq, Sq, D = q.shape
    Hkv = k.shape[1]
    rep = Hq // Hkv
    k = (lambda x, n, axis: torch.repeat_interleave(x, n, dim=axis))(k, rep, axis=1)
    v = (lambda x, n, axis: torch.repeat_interleave(x, n, dim=axis))(v, rep, axis=1)
    scale = D ** -0.5
    scores = torch.einsum("bhqd,bhkd->bhqk", q, k) * scale
    p = _softmax(scores, axis=-1)
    return torch.einsum("bhqk,bhkd->bhqd", p, v)
```

```cpp
#include <cuda_runtime.h>
#include <cuda_bf16.h>
#include <cuda.h>
#include <stdint.h>

namespace {

constexpr int kH = 32;
constexpr int kS = 2048;
constexpr int kD = 192;
constexpr int kBM = 128;
constexpr int kBN = 128;
constexpr int kNBlk = kS / kBN;
constexpr int kNumCtas = 128;
constexpr int kTilesPerCta = kH * (kS / kBM) / kNumCtas;
constexpr int kTotal = kTilesPerCta * kNBlk;

constexpr int kQBytesWG = 2 * 8192;
constexpr int kTileBytes = 3 * 16384;
constexpr int kOffQ = 0;
constexpr int kOffRing = 2 * kQBytesWG;
constexpr int kOffBar = kOffRing + 4 * kTileBytes;
constexpr int kSmemBytes = kOffBar + 256 + 1024;

constexpr int kBarFull = 0, kBarEmpty = 4, kBarQFull = 8, kBarQEmpty = 10, kBarOFull = 12, kBarStart = 14;

__device__ __forceinline__ void wgmma_rs_n128(float (&d)[64], uint32_t a0, uint32_t a1, uint32_t a2, uint32_t a3, uint64_t descB, int scaleD) {
  asm volatile("{\n.reg .pred p;\nsetp.ne.b32 p, %69, 0;\n"
    "wgmma.mma_async.sync.aligned.m64n128k16.f32.bf16.bf16 "
    "{%0, %1, %2, %3, %4, %5, %6, %7, %8, %9, %10, %11, %12, %13, %14, %15, %16, %17, %18, %19, %20, %21, %22, %23, %24, %25, %26, %27, %28, %29, %30, %31, %32, %33, %34, %35, %36, %37, %38, %39, %40, %41, %42, %43, %44, %45, %46, %47, %48, %49, %50, %51, %52, %53, %54, %55, %56, %57, %58, %59, %60, %61, %62, %63}, "
    "{%64, %65, %66, %67}, %68, p, 1, 1, 0;\n}\n"
    : "+f"(d[0]), "+f"(d[1]), "+f"(d[2]), "+f"(d[3]), "+f"(d[4]), "+f"(d[5]), "+f"(d[6]), "+f"(d[7]), "+f"(d[8]), "+f"(d[9]), "+f"(d[10]), "+f"(d[11]), "+f"(d[12]), "+f"(d[13]), "+f"(d[14]), "+f"(d[15]), "+f"(d[16]), "+f"(d[17]), "+f"(d[18]), "+f"(d[19]), "+f"(d[20]), "+f"(d[21]), "+f"(d[22]), "+f"(d[23]), "+f"(d[24]), "+f"(d[25]), "+f"(d[26]), "+f"(d[27]), "+f"(d[28]), "+f"(d[29]), "+f"(d[30]), "+f"(d[31]), "+f"(d[32]), "+f"(d[33]), "+f"(d[34]), "+f"(d[35]), "+f"(d[36]), "+f"(d[37]), "+f"(d[38]), "+f"(d[39]), "+f"(d[40]), "+f"(d[41]), "+f"(d[42]), "+f"(d[43]), "+f"(d[44]), "+f"(d[45]), "+f"(d[46]), "+f"(d[47]), "+f"(d[48]), "+f"(d[49]), "+f"(d[50]), "+f"(d[51]), "+f"(d[52]), "+f"(d[53]), "+f"(d[54]), "+f"(d[55]), "+f"(d[56]), "+f"(d[57]), "+f"(d[58]), "+f"(d[59]), "+f"(d[60]), "+f"(d[61]), "+f"(d[62]), "+f"(d[63])
    : "r"(a0), "r"(a1), "r"(a2), "r"(a3), "l"(descB), "r"(scaleD));
}

__device__ __forceinline__ void wgmma_rs_n192_tb(float (&d)[96], uint32_t a0, uint32_t a1, uint32_t a2, uint32_t a3, uint64_t descB, int scaleD) {
  asm volatile("{\n.reg .pred p;\nsetp.ne.b32 p, %101, 0;\n"
    "wgmma.mma_async.sync.aligned.m64n192k16.f32.bf16.bf16 "
    "{%0, %1, %2, %3, %4, %5, %6, %7, %8, %9, %10, %11, %12, %13, %14, %15, %16, %17, %18, %19, %20, %21, %22, %23, %24, %25, %26, %27, %28, %29, %30, %31, %32, %33, %34, %35, %36, %37, %38, %39, %40, %41, %42, %43, %44, %45, %46, %47, %48, %49, %50, %51, %52, %53, %54, %55, %56, %57, %58, %59, %60, %61, %62, %63, %64, %65, %66, %67, %68, %69, %70, %71, %72, %73, %74, %75, %76, %77, %78, %79, %80, %81, %82, %83, %84, %85, %86, %87, %88, %89, %90, %91, %92, %93, %94, %95}, "
    "{%96, %97, %98, %99}, %100, p, 1, 1, 1;\n}\n"
    : "+f"(d[0]), "+f"(d[1]), "+f"(d[2]), "+f"(d[3]), "+f"(d[4]), "+f"(d[5]), "+f"(d[6]), "+f"(d[7]), "+f"(d[8]), "+f"(d[9]), "+f"(d[10]), "+f"(d[11]), "+f"(d[12]), "+f"(d[13]), "+f"(d[14]), "+f"(d[15]), "+f"(d[16]), "+f"(d[17]), "+f"(d[18]), "+f"(d[19]), "+f"(d[20]), "+f"(d[21]), "+f"(d[22]), "+f"(d[23]), "+f"(d[24]), "+f"(d[25]), "+f"(d[26]), "+f"(d[27]), "+f"(d[28]), "+f"(d[29]), "+f"(d[30]), "+f"(d[31]), "+f"(d[32]), "+f"(d[33]), "+f"(d[34]), "+f"(d[35]), "+f"(d[36]), "+f"(d[37]), "+f"(d[38]), "+f"(d[39]), "+f"(d[40]), "+f"(d[41]), "+f"(d[42]), "+f"(d[43]), "+f"(d[44]), "+f"(d[45]), "+f"(d[46]), "+f"(d[47]), "+f"(d[48]), "+f"(d[49]), "+f"(d[50]), "+f"(d[51]), "+f"(d[52]), "+f"(d[53]), "+f"(d[54]), "+f"(d[55]), "+f"(d[56]), "+f"(d[57]), "+f"(d[58]), "+f"(d[59]), "+f"(d[60]), "+f"(d[61]), "+f"(d[62]), "+f"(d[63]), "+f"(d[64]), "+f"(d[65]), "+f"(d[66]), "+f"(d[67]), "+f"(d[68]), "+f"(d[69]), "+f"(d[70]), "+f"(d[71]), "+f"(d[72]), "+f"(d[73]), "+f"(d[74]), "+f"(d[75]), "+f"(d[76]), "+f"(d[77]), "+f"(d[78]), "+f"(d[79]), "+f"(d[80]), "+f"(d[81]), "+f"(d[82]), "+f"(d[83]), "+f"(d[84]), "+f"(d[85]), "+f"(d[86]), "+f"(d[87]), "+f"(d[88]), "+f"(d[89]), "+f"(d[90]), "+f"(d[91]), "+f"(d[92]), "+f"(d[93]), "+f"(d[94]), "+f"(d[95])
    : "r"(a0), "r"(a1), "r"(a2), "r"(a3), "l"(descB), "r"(scaleD));
}

__device__ __forceinline__ void wgmma_rs_n64_tb(float (&d)[32], uint32_t a0, uint32_t a1, uint32_t a2, uint32_t a3, uint64_t descB, int scaleD) {
  asm volatile("{\n.reg .pred p;\nsetp.ne.b32 p, %37, 0;\n"
    "wgmma.mma_async.sync.aligned.m64n64k16.f32.bf16.bf16 "
    "{%0, %1, %2, %3, %4, %5, %6, %7, %8, %9, %10, %11, %12, %13, %14, %15, %16, %17, %18, %19, %20, %21, %22, %23, %24, %25, %26, %27, %28, %29, %30, %31}, "
    "{%32, %33, %34, %35}, %36, p, 1, 1, 1;\n}\n"
    : "+f"(d[0]), "+f"(d[1]), "+f"(d[2]), "+f"(d[3]), "+f"(d[4]), "+f"(d[5]), "+f"(d[6]), "+f"(d[7]), "+f"(d[8]), "+f"(d[9]), "+f"(d[10]), "+f"(d[11]), "+f"(d[12]), "+f"(d[13]), "+f"(d[14]), "+f"(d[15]), "+f"(d[16]), "+f"(d[17]), "+f"(d[18]), "+f"(d[19]), "+f"(d[20]), "+f"(d[21]), "+f"(d[22]), "+f"(d[23]), "+f"(d[24]), "+f"(d[25]), "+f"(d[26]), "+f"(d[27]), "+f"(d[28]), "+f"(d[29]), "+f"(d[30]), "+f"(d[31])
    : "r"(a0), "r"(a1), "r"(a2), "r"(a3), "l"(descB), "r"(scaleD));
}

__device__ __forceinline__ void wgmma_ss_n128(float (&d)[64], uint64_t descA, uint64_t descB, int scaleD) {
  asm volatile("{\n.reg .pred p;\nsetp.ne.b32 p, %66, 0;\n"
    "wgmma.mma_async.sync.aligned.m64n128k16.f32.bf16.bf16 "
    "{%0, %1, %2, %3, %4, %5, %6, %7, %8, %9, %10, %11, %12, %13, %14, %15, %16, %17, %18, %19, %20, %21, %22, %23, %24, %25, %26, %27, %28, %29, %30, %31, %32, %33, %34, %35, %36, %37, %38, %39, %40, %41, %42, %43, %44, %45, %46, %47, %48, %49, %50, %51, %52, %53, %54, %55, %56, %57, %58, %59, %60, %61, %62, %63}, "
    "%64, %65, p, 1, 1, 0, 0;\n}\n"
    : "+f"(d[0]), "+f"(d[1]), "+f"(d[2]), "+f"(d[3]), "+f"(d[4]), "+f"(d[5]), "+f"(d[6]), "+f"(d[7]), "+f"(d[8]), "+f"(d[9]), "+f"(d[10]), "+f"(d[11]), "+f"(d[12]), "+f"(d[13]), "+f"(d[14]), "+f"(d[15]), "+f"(d[16]), "+f"(d[17]), "+f"(d[18]), "+f"(d[19]), "+f"(d[20]), "+f"(d[21]), "+f"(d[22]), "+f"(d[23]), "+f"(d[24]), "+f"(d[25]), "+f"(d[26]), "+f"(d[27]), "+f"(d[28]), "+f"(d[29]), "+f"(d[30]), "+f"(d[31]), "+f"(d[32]), "+f"(d[33]), "+f"(d[34]), "+f"(d[35]), "+f"(d[36]), "+f"(d[37]), "+f"(d[38]), "+f"(d[39]), "+f"(d[40]), "+f"(d[41]), "+f"(d[42]), "+f"(d[43]), "+f"(d[44]), "+f"(d[45]), "+f"(d[46]), "+f"(d[47]), "+f"(d[48]), "+f"(d[49]), "+f"(d[50]), "+f"(d[51]), "+f"(d[52]), "+f"(d[53]), "+f"(d[54]), "+f"(d[55]), "+f"(d[56]), "+f"(d[57]), "+f"(d[58]), "+f"(d[59]), "+f"(d[60]), "+f"(d[61]), "+f"(d[62]), "+f"(d[63])
    : "l"(descA), "l"(descB), "r"(scaleD));
}

__device__ __forceinline__ void wg_fence() { asm volatile("wgmma.fence.sync.aligned;\n" ::: "memory"); }
__device__ __forceinline__ void wg_commit() { asm volatile("wgmma.commit_group.sync.aligned;\n" ::: "memory"); }
template <int N> __device__ __forceinline__ void wg_wait() { asm volatile("wgmma.wait_group.sync.aligned %0;\n" ::"n"(N) : "memory"); }

template <int N> __device__ __forceinline__ void fence_regs(float (&r)[N]) {
#pragma unroll
  for (int i = 0; i < N; i++) asm volatile("" : "+f"(r[i])::"memory");
}
template <int N> __device__ __forceinline__ void fence_regs(uint32_t (&r)[N]) {
#pragma unroll
  for (int i = 0; i < N; i++) asm volatile("" : "+r"(r[i])::"memory");
}

__device__ __forceinline__ uint64_t make_desc(uint32_t addr, uint32_t lbo, uint32_t sbo) {
  uint64_t d = 0;
  d |= (uint64_t)((addr & 0x3FFFF) >> 4);
  d |= (uint64_t)((lbo >> 4) & 0x3FFF) << 16;
  d |= (uint64_t)((sbo >> 4) & 0x3FFF) << 32;
  d |= (uint64_t)1 << 62;
  return d;
}

__device__ __forceinline__ void mbar_init(uint32_t bar, uint32_t count) {
  asm volatile("mbarrier.init.shared::cta.b64 [%0], %1;" ::"r"(bar), "r"(count) : "memory");
}
__device__ __forceinline__ void mbar_expect_tx(uint32_t bar, uint32_t bytes) {
  asm volatile("mbarrier.arrive.expect_tx.shared::cta.b64 _, [%0], %1;" ::"r"(bar), "r"(bytes) : "memory");
}
__device__ __forceinline__ void mbar_arrive(uint32_t bar, uint32_t n) {
  asm volatile("mbarrier.arrive.shared::cta.b64 _, [%0], %1;" ::"r"(bar), "r"(n) : "memory");
}
__device__ __forceinline__ void mbar_arrive_lane0(uint32_t bar, int lane) {
  asm volatile(
      "{\n.reg .pred p;\n"
      "setp.eq.u32 p, %1, 0;\n"
      "@p mbarrier.arrive.shared::cta.b64 _, [%0];\n}\n" ::"r"(bar), "r"(lane) : "memory");
}
__device__ __forceinline__ void mbar_wait(uint32_t bar, uint32_t parity) {
  asm volatile(
      "{\n.reg .pred p;\n.reg .u32 n;\n"
      "mov.u32 n, 0;\n"
      "LAB_WAIT:\n"
      "mbarrier.try_wait.parity.shared::cta.b64 p, [%0], %1;\n"
      "@p bra LAB_DONE;\n"
      "add.u32 n, n, 1;\n"
      "setp.lt.u32 p, n, 4194304;\n"
      "@p bra LAB_WAIT;\n"
      "trap;\n"
      "LAB_DONE:\n}\n" ::"r"(bar), "r"(parity) : "memory");
}
__device__ __forceinline__ void mbar_wait_sleepy(uint32_t bar, uint32_t parity) {
  asm volatile(
      "{\n.reg .pred p;\n.reg .u32 n;\n"
      "mov.u32 n, 0;\n"
      "LAB_WAIT:\n"
      "mbarrier.try_wait.parity.shared::cta.b64 p, [%0], %1, 20000;\n"
      "@p bra LAB_DONE;\n"
      "add.u32 n, n, 1;\n"
      "setp.lt.u32 p, n, 100000;\n"
      "@p bra LAB_WAIT;\n"
      "trap;\n"
      "LAB_DONE:\n}\n" ::"r"(bar), "r"(parity) : "memory");
}
__device__ __forceinline__ bool mbar_test(uint32_t bar, uint32_t parity) {
  uint32_t ok;
  asm volatile(
      "{\n.reg .pred p;\n"
      "mbarrier.test_wait.parity.shared::cta.b64 p, [%1], %2;\n"
      "selp.u32 %0, 1, 0, p;\n}\n"
      : "=r"(ok) : "r"(bar), "r"(parity) : "memory");
  return ok != 0;
}

__device__ __forceinline__ void tma_load(uint32_t dst, const CUtensorMap* map, uint32_t bar, int c0, int c1) {
  asm volatile(
      "cp.async.bulk.tensor.2d.shared::cluster.global.mbarrier::complete_tx::bytes [%0], [%1, {%3, %4}], [%2];"
      ::"r"(dst), "l"(map), "r"(bar), "r"(c0), "r"(c1) : "memory");
}
__device__ __forceinline__ void tma_prefetch(const CUtensorMap* map, int c0, int c1) {
  asm volatile("cp.async.bulk.prefetch.tensor.2d.L2.global [%0, {%1, %2}];" ::"l"(map), "r"(c0), "r"(c1) : "memory");
}
__device__ __forceinline__ void tma_store(const CUtensorMap* map, uint32_t src, int c0, int c1) {
  asm volatile("cp.async.bulk.tensor.2d.global.shared::cta.bulk_group [%0, {%2, %3}], [%1];"
               ::"l"(map), "r"(src), "r"(c0), "r"(c1) : "memory");
}
__device__ __forceinline__ void tma_store_warp(const CUtensorMap* map, uint32_t src, int col, int row) {
  asm volatile(
      "{\n.reg .pred p;\n"
      "fence.proxy.async.shared::cta;\n"
      "bar.warp.sync 0xffffffff;\n"
      "elect.sync _|p, 0xffffffff;\n"
      "@p cp.async.bulk.tensor.2d.global.shared::cta.bulk_group [%0, {%2, %3}], [%1];\n"
      "@p cp.async.bulk.commit_group;\n}\n"
      ::"l"(map), "r"(src), "r"(col), "r"(row) : "memory");
}
__device__ __forceinline__ void ldsm_x4(uint32_t addr, uint32_t& a, uint32_t& b, uint32_t& c, uint32_t& d) {
  asm volatile("ldmatrix.sync.aligned.m8n8.x4.shared.b16 {%0, %1, %2, %3}, [%4];" : "=r"(a), "=r"(b), "=r"(c), "=r"(d) : "r"(addr) : "memory");
}
__device__ __forceinline__ void stsm_x4(uint32_t addr, uint32_t a, uint32_t b, uint32_t c, uint32_t d) {
  asm volatile("stmatrix.sync.aligned.m8n8.x4.shared.b16 [%0], {%1, %2, %3, %4};" ::"r"(addr), "r"(a), "r"(b), "r"(c), "r"(d) : "memory");
}
__device__ __forceinline__ void bar_sync(int id) { asm volatile("bar.sync %0, 256;" ::"r"(id) : "memory"); }
__device__ __forceinline__ void bar_arrive(int id) { asm volatile("bar.arrive %0, 256;" ::"r"(id) : "memory"); }
__device__ __forceinline__ float ex2(float x) {
  float y;
  asm("ex2.approx.ftz.f32 %0, %1;" : "=f"(y) : "f"(x));
  return y;
}
__device__ __forceinline__ float rcp_approx(float x) {
  float y;
  asm("rcp.approx.ftz.f32 %0, %1;" : "=f"(y) : "f"(x));
  return y;
}
__device__ __forceinline__ uint32_t pack_bf16(float lo, float hi) {
  uint32_t r;
  asm("cvt.rn.bf16x2.f32 %0, %1, %2;" : "=r"(r) : "f"(hi), "f"(lo));
  return r;
}
__device__ __forceinline__ uint32_t ldg32(const void* p) {
  uint32_t r;
  asm volatile("ld.global.nc.b32 %0, [%1];" : "=r"(r) : "l"(p) : "memory");
  return r;
}

constexpr int kQkHead = 7;
constexpr int kQkTail = 2;
constexpr int kEpi1 = 6;
constexpr int kEpi2 = 10;
constexpr int kOEarly = 8;

template <int K0, int K1>
__device__ __forceinline__ void issue_qk(float (&s)[64], const uint32_t (&qr)[16], uint64_t descQ, uint64_t descK) {
#pragma unroll
  for (int k = K0; k < K1; k++) {
    const uint32_t offA = ((k / 4) * 8192 + (k % 4) * 32) >> 4;
    const uint32_t offB = ((k / 4) * 16384 + (k % 4) * 32) >> 4;
    if (k < 8) wgmma_ss_n128(s, descQ + offA, descK + offB, k > 0);
    else wgmma_rs_n128(s, qr[4 * (k - 8)], qr[4 * (k - 8) + 1], qr[4 * (k - 8) + 2], qr[4 * (k - 8) + 3], descK + offB, 1);
  }
  wg_commit();
}
__device__ __forceinline__ void issue_pv(float (&o)[96], const uint32_t (&p)[32], uint64_t descV, int accumulate) {
#pragma unroll
  for (int k = 0; k < 8; k++) {
    wgmma_rs_n192_tb(o, p[4 * k], p[4 * k + 1], p[4 * k + 2], p[4 * k + 3], descV + ((k * 2048) >> 4), k > 0 ? 1 : accumulate);
  }
  wg_commit();
}
__device__ __forceinline__ void issue_pv_chunk(float (&oc)[32], const uint32_t (&p)[32], uint64_t descV) {
#pragma unroll
  for (int k = 0; k < 8; k++)
    wgmma_rs_n64_tb(oc, p[4 * k], p[4 * k + 1], p[4 * k + 2], p[4 * k + 3], descV + ((k * 2048) >> 4), 1);
  wg_commit();
}

__device__ __forceinline__ void load_q_regs(uint32_t (&qr)[16], const __nv_bfloat16* qrow) {
#pragma unroll
  for (int k = 0; k < 4; k++) {
    qr[4 * k + 0] = ldg32(qrow + 16 * k);
    qr[4 * k + 1] = ldg32(qrow + 16 * k + 8 * kD);
    qr[4 * k + 2] = ldg32(qrow + 16 * k + 8);
    qr[4 * k + 3] = ldg32(qrow + 16 * k + 8 * kD + 8);
  }
}

template <int J0, int J1, int N>
__device__ __forceinline__ void stage_o(const float (&o)[N], float inv0, float inv1, uint32_t lane_addr) {
#pragma unroll
  for (int jj = J0; jj < J1; jj++) {
    const uint32_t x0 = pack_bf16(o[8 * jj + 0] * inv0, o[8 * jj + 1] * inv0);
    const uint32_t x1 = pack_bf16(o[8 * jj + 2] * inv1, o[8 * jj + 3] * inv1);
    const uint32_t x2 = pack_bf16(o[8 * jj + 4] * inv0, o[8 * jj + 5] * inv0);
    const uint32_t x3 = pack_bf16(o[8 * jj + 6] * inv1, o[8 * jj + 7] * inv1);
    stsm_x4((lane_addr ^ ((jj % 4) * 32)) + (jj / 4) * 8192, x0, x1, x2, x3);
  }
}
__device__ __forceinline__ void finish_l(float& l0, float& l1) {
  l0 += __shfl_xor_sync(0xffffffffu, l0, 1);
  l1 += __shfl_xor_sync(0xffffffffu, l1, 1);
  l0 += __shfl_xor_sync(0xffffffffu, l0, 2);
  l1 += __shfl_xor_sync(0xffffffffu, l1, 2);
  l0 = rcp_approx(l0); l1 = rcp_approx(l1);
}

constexpr float kScaleLog2 = 0.07216878364870322f * 1.4426950408889634f;

constexpr float kLimit = 65536.f;

__device__ __forceinline__ void row_max(const float (&s)[64], float& n0, float& n1) {
  float a0 = fmaxf(s[0], s[1]), a1 = fmaxf(s[2], s[3]), b0 = fmaxf(s[4], s[5]), b1 = fmaxf(s[6], s[7]);
#pragma unroll
  for (int j = 2; j < 16; j += 2) {
    a0 = fmaxf(a0, fmaxf(s[4 * j], s[4 * j + 1]));
    a1 = fmaxf(a1, fmaxf(s[4 * j + 2], s[4 * j + 3]));
    b0 = fmaxf(b0, fmaxf(s[4 * j + 4], s[4 * j + 5]));
    b1 = fmaxf(b1, fmaxf(s[4 * j + 6], s[4 * j + 7]));
  }
  n0 = fmaxf(a0, b0); n1 = fmaxf(a1, b1);
  n0 = fmaxf(n0, __shfl_xor_sync(0xffffffffu, n0, 1));
  n1 = fmaxf(n1, __shfl_xor_sync(0xffffffffu, n1, 1));
  n0 = fmaxf(n0, __shfl_xor_sync(0xffffffffu, n0, 2));
  n1 = fmaxf(n1, __shfl_xor_sync(0xffffffffu, n1, 2));
  n0 *= kScaleLog2; n1 *= kScaleLog2;
}

__device__ __forceinline__ bool row_max_fast(const float (&s)[64], float& n0, float& n1) {
  int a0 = max(__float_as_int(s[0]), __float_as_int(s[1])), a1 = max(__float_as_int(s[2]), __float_as_int(s[3]));
  int b0 = max(__float_as_int(s[4]), __float_as_int(s[5])), b1 = max(__float_as_int(s[6]), __float_as_int(s[7]));
#pragma unroll
  for (int j = 2; j < 16; j += 2) {
    a0 = __vimax3_s32(a0, __float_as_int(s[4 * j]), __float_as_int(s[4 * j + 1]));
    a1 = __vimax3_s32(a1, __float_as_int(s[4 * j + 2]), __float_as_int(s[4 * j + 3]));
    b0 = __vimax3_s32(b0, __float_as_int(s[4 * j + 4]), __float_as_int(s[4 * j + 5]));
    b1 = __vimax3_s32(b1, __float_as_int(s[4 * j + 6]), __float_as_int(s[4 * j + 7]));
  }
  a0 = max(a0, b0); a1 = max(a1, b1);
  a0 = max(a0, __shfl_xor_sync(0xffffffffu, a0, 1));
  a1 = max(a1, __shfl_xor_sync(0xffffffffu, a1, 1));
  a0 = max(a0, __shfl_xor_sync(0xffffffffu, a0, 2));
  a1 = max(a1, __shfl_xor_sync(0xffffffffu, a1, 2));
  n0 = __int_as_float(a0) * kScaleLog2; n1 = __int_as_float(a1) * kScaleLog2;
  return (a0 | a1) >= 0;
}

__device__ __forceinline__ void exp_pass(const float (&s)[64], uint32_t (&p)[32], float mc0, float mc1, float& r0, float& r1) {
  r0 = 0.f; r1 = 0.f;
#pragma unroll
  for (int j = 0; j < 16; j++) {
    const float e0 = ex2(fmaf(s[4 * j], kScaleLog2, -mc0));
    const float e1 = ex2(fmaf(s[4 * j + 1], kScaleLog2, -mc0));
    const float e2 = ex2(fmaf(s[4 * j + 2], kScaleLog2, -mc1));
    const float e3 = ex2(fmaf(s[4 * j + 3], kScaleLog2, -mc1));
    if (j == 0) { r0 = e0; r1 = e2; } else { r0 += e0; r1 += e2; }
    r0 += e1; r1 += e3;
    p[2 * j] = pack_bf16(e0, e1);
    p[2 * j + 1] = pack_bf16(e2, e3);
  }
}

__global__ void __launch_bounds__(384, 1)
attn_fwd_kernel(const __grid_constant__ CUtensorMap tmQ, const __grid_constant__ CUtensorMap tmK,
                const __grid_constant__ CUtensorMap tmV, const __grid_constant__ CUtensorMap tmO,
                const __nv_bfloat16* __restrict__ gQ) {
  extern __shared__ uint8_t smem_raw[];
  const uint32_t sbase = ((uint32_t)__cvta_generic_to_shared(smem_raw) + 1023u) & ~1023u;
  const uint32_t bars = sbase + kOffBar;
  const uint32_t ring = sbase + kOffRing;
  const int tid = threadIdx.x;
  const int wg = __shfl_sync(0xffffffffu, tid >> 7, 0);
  const int warp = __shfl_sync(0xffffffffu, tid >> 5, 0);
  const int lane = tid & 31;
  const int cta = blockIdx.x;

  if (wg == 2) {
    asm volatile("setmaxnreg.dec.sync.aligned.u32 24;\n");
    if (tid == 256) {
      mbar_init(bars + 8 * kBarStart, 1);
      mbar_init(bars + 8 * (kBarStart + 1), 1);
      mbar_init(bars + 8 * (kBarFull + 1), 1);
      asm volatile("fence.mbarrier_init.release.cluster;" ::: "memory");
#pragma unroll
      for (int c = 0; c < 3; c++) {
        const uint32_t bar = bars + 8 * (c < 2 ? kBarStart + c : kBarFull + 1);
        mbar_expect_tx(bar, 16384 + 8192);
        tma_load(c < 2 ? sbase + kOffQ + c * 8192 : ring, &tmQ, bar, c * 64, cta * kBM);
        tma_load(ring + kTileBytes + c * 16384, &tmK, bar, c * 64, (cta / 16) * kS);
      }
    } else if (tid == 288) {
#pragma unroll
      for (int i = 0; i < 4; i++) {
        if (i != 1) mbar_init(bars + 8 * (kBarFull + i), 1);
        mbar_init(bars + 8 * (kBarEmpty + i), 8);
      }
#pragma unroll
      for (int i = 0; i < 2; i++) {
        mbar_init(bars + 8 * (kBarQFull + i), 1);
        mbar_init(bars + 8 * (kBarQEmpty + i), 4);
        mbar_init(bars + 8 * (kBarOFull + i), 4);
      }
      asm volatile("fence.mbarrier_init.release.cluster;" ::: "memory");
      mbar_arrive(bars + 8 * kBarFull, 1);
      mbar_arrive(bars + 8 * kBarQFull, 1);
    } else if (tid == 320) {
      asm volatile("prefetch.tensormap [%0];" ::"l"(&tmV) : "memory");
      asm volatile("prefetch.tensormap [%0];" ::"l"(&tmO) : "memory");
    }
    __syncwarp();
    asm volatile("bar.sync 3, 384;" ::: "memory");
    if (lane == 0) {
      if (warp == 8) {
        int pos = 2;
#pragma unroll 1
        for (int e = 1; e < 2 * kTotal; e++) {
          const int g = e >> 1;
          const bool isV = e & 1;
          const CUtensorMap* map = isV ? &tmV : &tmK;
          const int tile = cta + (g / kNBlk) * kNumCtas;
          const int row = (tile / 16) * kS + (g % kNBlk) * kBN;
          const int slot = pos & 3;
          mbar_wait_sleepy(bars + 8 * (kBarEmpty + slot), ((pos >> 2) & 1) ^ 1);
          mbar_expect_tx(bars + 8 * (kBarFull + slot), kTileBytes);
#pragma unroll
          for (int c = 0; c < 3; c++) tma_load(ring + slot * kTileBytes + c * 16384, map, bars + 8 * (kBarFull + slot), c * 64, row);
          pos++;
          if (isV && (g % kNBlk) == 0 && g > 0) {
            mbar_wait_sleepy(bars + 8 * (kBarEmpty + (pos & 3)), ((pos >> 2) & 1) ^ 1);
            mbar_arrive(bars + 8 * (kBarFull + (pos & 3)), 1);
            pos++;
          }
          if (e == 2 * kTotal - 4) asm volatile("prefetch.tensormap [%0];" ::"l"(&tmO) : "memory");
          if (g + kNBlk < kTotal) {
            if ((e % (2 * kNBlk)) == 26) {
              if ((cta & 15) < 6) tma_prefetch(&tmK, ((cta & 15) % 3) * 64, ((tile + kNumCtas) / 16) * kS + (1 + (cta & 15) / 3) * kBN);
            } else if ((e % (2 * kNBlk)) == 22) {
#pragma unroll
              for (int i = 0; i < 6; i++) tma_prefetch(&tmQ, (i % 3) * 64, (tile + kNumCtas) * kBM + (i / 3) * 64);
            }
          }
        }
      } else if (warp == 10) {
#pragma unroll 1
        for (int t = 0; t + 1 < kTilesPerCta; t++) {
          const int po = 2 * (16 * t + 16) + t + 3;
          const uint32_t stg = ring + (po & 3) * kTileBytes;
          const int row = (cta + t * kNumCtas) * kBM;
          mbar_wait_sleepy(bars + 8 * kBarOFull, t & 1);
#pragma unroll 1
          for (int i = 0; i < kOEarly; i++) tma_store(&tmO, stg + i * 2048, (i >> 2) * 64, row + (i & 3) * 16);
          mbar_wait_sleepy(bars + 8 * (kBarFull + ((po + 1) & 3)), ((po + 1) >> 2) & 1);
#pragma unroll 1
          for (int i = kOEarly; i < 12; i++) tma_store(&tmO, stg + i * 2048, (i >> 2) * 64, row + (i & 3) * 16);
          mbar_wait_sleepy(bars + 8 * (kBarOFull + 1), t & 1);
#pragma unroll 1
          for (int i = 0; i < 12; i++) tma_store(&tmO, stg + 24576 + i * 2048, (i >> 2) * 64, row + 64 + (i & 3) * 16);
          asm volatile("cp.async.bulk.commit_group;" ::: "memory");
          asm volatile("cp.async.bulk.wait_group.read 0;" ::: "memory");
          mbar_arrive(bars + 8 * (kBarEmpty + (po & 3)), 8);
        }
      } else if (warp == 9) {
        __nanosleep(200);
        mbar_expect_tx(bars + 8 * (kBarQFull + 1), kQBytesWG + 8192);
#pragma unroll
        for (int c = 0; c < 3; c++)
          tma_load(c < 2 ? sbase + kOffQ + kQBytesWG + c * 8192 : ring + 8192, &tmQ, bars + 8 * (kBarQFull + 1), c * 64, cta * kBM + 64);
#pragma unroll 1
        for (int t = 1; t < kTilesPerCta; t++) {
          const int row = (cta + t * kNumCtas) * kBM;
#pragma unroll
          for (int w = 0; w < 2; w++) {
            mbar_wait_sleepy(bars + 8 * (kBarQEmpty + w), (t & 1) ^ 1);
            mbar_expect_tx(bars + 8 * (kBarQFull + w), kQBytesWG);
            tma_load(sbase + kOffQ + w * kQBytesWG, &tmQ, bars + 8 * (kBarQFull + w), 0, row + w * 64);
            tma_load(sbase + kOffQ + w * kQBytesWG + 8192, &tmQ, bars + 8 * (kBarQFull + w), 64, row + w * 64);
          }
        }
      }
    }
  } else {
    asm volatile("setmaxnreg.inc.sync.aligned.u32 240;\n");
    const int wrow = cta * kBM + warp * 16;
    const __nv_bfloat16* qptr = gQ + ((size_t)wrow + (lane >> 2)) * kD + 128 + 2 * (lane & 3);
    uint32_t qr[16];
    asm volatile("barrier.sync 3, 384;" ::: "memory");

    const uint64_t descQ = make_desc(sbase + kOffQ + wg * kQBytesWG, 16, 1024);
    const uint64_t descK0 = make_desc(ring, 16, 1024);
    const uint64_t descV0 = make_desc(ring, 16384, 1024);
    const int my_bar = 1 + wg, other_bar = 2 - wg;
    const uint32_t lane_off = ((warp & 3) * 16 + ((lane >> 3) & 1) * 8 + (lane & 7)) * 128 + (((lane >> 4) ^ (lane & 7)) << 4);

    float o[96];
    float s[64];
    uint32_t p[32];
    float mc0 = 0.f, mc1 = 0.f, l0 = 0.f, l1 = 0.f;
    float limit = kLimit;
    if (wg == 1) bar_arrive(1);

    mbar_wait(bars + 8 * (kBarQFull + wg), 0);
    mbar_wait(bars + 8 * kBarStart, 0);
    bar_sync(my_bar);
    wg_fence();
    issue_qk<0, 4>(s, qr, descQ, descK0 + (kTileBytes >> 4));
    mbar_wait(bars + 8 * (kBarStart + 1), 0);
    wg_fence();
    issue_qk<4, 8>(s, qr, descQ, descK0 + (kTileBytes >> 4));
    mbar_wait(bars + 8 * (kBarFull + 1), 0);
#pragma unroll
    for (int k = 0; k < 4; k++)
      ldsm_x4((ring + wg * 8192 + lane_off) ^ (k * 32), qr[4 * k], qr[4 * k + 1], qr[4 * k + 2], qr[4 * k + 3]);
    fence_regs(qr);
    wg_fence();
    issue_qk<8, 12 - kQkTail>(s, qr, descQ, descK0 + (kTileBytes >> 4));
    issue_qk<12 - kQkTail, 12>(s, qr, descQ, descK0 + (kTileBytes >> 4));
    wg_wait<1>();
    bar_arrive(other_bar);
    wg_wait<0>();
    fence_regs(s);
    mbar_arrive_lane0(bars + 8 * kBarEmpty, lane);
    mbar_arrive_lane0(bars + 8 * (kBarEmpty + 1), lane);

    uint32_t pv = 2;
    bool v_ready = false;
#pragma unroll 1
    for (uint32_t g = 0;; g = __shfl_sync(0xffffffffu, g + 1, 0)) {
      const uint32_t jb = g % kNBlk;
      if (__builtin_expect(((jb + 1) % kNBlk) < 2, 0)) {
        if (jb == 0) {
          if (!row_max_fast(s, mc0, mc1)) limit = -1.f;
          l0 = 0.f; l1 = 0.f;
          if (g > 0) {
            asm volatile("fence.proxy.async.shared::cta;" ::: "memory");
            __syncwarp();
            mbar_arrive_lane0(bars + 8 * (kBarOFull + wg), lane);
          }
        } else if (g + 1 < kTotal) {
          mbar_arrive_lane0(bars + 8 * (kBarQEmpty + wg), lane);
          qptr += (size_t)kNumCtas * kBM * kD;
          load_q_regs(qr, qptr);
        }
      }
      float r0, r1;
      exp_pass(s, p, mc0, mc1, r0, r1);
      if (__builtin_expect(__any_sync(0xffffffffu, !(r0 + r1 <= limit)), 0)) {
        float n0, n1;
        row_max(s, n0, n1);
        n0 = fmaxf(n0, mc0); n1 = fmaxf(n1, mc1);
        const float al0 = ex2(mc0 - n0), al1 = ex2(mc1 - n1);
        l0 *= al0; l1 *= al1;
#pragma unroll
        for (int j = 0; j < 24; j++) {
          o[4 * j] *= al0; o[4 * j + 1] *= al0; o[4 * j + 2] *= al1; o[4 * j + 3] *= al1;
        }
        mc0 = n0; mc1 = n1;
        limit = kLimit;
        exp_pass(s, p, mc0, mc1, r0, r1);
      }
      l0 += r0; l1 += r1;
      if (__builtin_expect(!v_ready, 0)) {
        mbar_wait(bars + 8 * (kBarFull + (pv & 3)), (pv >> 2) & 1);
        if (g + 1 == kTotal) break;
      }
      bar_sync(my_bar);
      fence_regs(p); fence_regs(o);
      wg_fence();
      issue_pv(o, p, descV0 + (pv & 3) * (kTileBytes >> 4), jb != 0);
      const uint32_t pk = pv + ((jb == 0 && g > 0) ? 2 : 1);
      const uint32_t po = pv + 3;
      const uint32_t stg = ring + (po & 3) * kTileBytes + wg * (3 * 8192);
      if (jb == kNBlk - 1) {
        finish_l(l0, l1);
        mbar_wait(bars + 8 * (kBarQFull + wg), ((g + 1) / kNBlk) & 1);
      }
      mbar_wait(bars + 8 * (kBarFull + (pk & 3)), (pk >> 2) & 1);
      const uint64_t descK = descK0 + (pk & 3) * (kTileBytes >> 4);
      fence_regs(s);
      wg_fence();
      issue_qk<0, kQkHead>(s, qr, descQ, descK);
      if (jb == kNBlk - 1) mbar_wait(bars + 8 * (kBarEmpty + (po & 3)), ((po >> 2) & 1) ^ 1);
      wg_wait<1>();
      fence_regs(o); fence_regs(p);
      mbar_arrive_lane0(bars + 8 * (kBarEmpty + (pv & 3)), lane);
      if (jb == kNBlk - 1) stage_o<0, kEpi1>(o, l0, l1, stg + lane_off);
      fence_regs(qr);
      wg_fence();
      issue_qk<kQkHead, 12 - kQkTail>(s, qr, descQ, descK);
      issue_qk<12 - kQkTail, 12>(s, qr, descQ, descK);
      pv = __shfl_sync(0xffffffffu, pk + 1, 0);
      v_ready = __all_sync(0xffffffffu, mbar_test(bars + 8 * (kBarFull + (pv & 3)), (pv >> 2) & 1)) && (g + 2 < kTotal);
      if (jb == kNBlk - 1) {
        stage_o<kEpi1, kEpi2>(o, l0, l1, stg + lane_off);
        bar_arrive(other_bar);
        stage_o<kEpi2, 12>(o, l0, l1, stg + lane_off);
      } else {
        wg_wait<1>();
        bar_arrive(other_bar);
      }
      wg_wait<0>();
      fence_regs(s); fence_regs(qr);
      mbar_arrive_lane0(bars + 8 * (kBarEmpty + (pk & 3)), lane);
    }
    {
      constexpr int pvl = 2 * (kTotal - 1) + 2 + (kTotal - 1 + kNBlk - 1) / kNBlk - 1;
      constexpr int po = pvl + 1;
      const uint32_t stg = ring + (po & 3) * kTileBytes + wg * (3 * 8192);
      const int orow = wrow + (kTilesPerCta - 1) * (kNumCtas * kBM);
      float oa[32], ob[32], oc[32];
#pragma unroll
      for (int i = 0; i < 32; i++) {
        asm volatile("mov.b32 %0, %1;" : "=f"(oa[i]) : "f"(o[i]));
        asm volatile("mov.b32 %0, %1;" : "=f"(ob[i]) : "f"(o[32 + i]));
        asm volatile("mov.b32 %0, %1;" : "=f"(oc[i]) : "f"(o[64 + i]));
      }
      const uint64_t descV = descV0 + (pvl & 3) * (kTileBytes >> 4);
      bar_sync(my_bar);
      fence_regs(p); fence_regs(oa); fence_regs(ob); fence_regs(oc);
      wg_fence();
      issue_pv_chunk(oa, p, descV);
      mbar_wait(bars + 8 * (kBarEmpty + (po & 3)), ((po >> 2) & 1) ^ 1);
      finish_l(l0, l1);
      wg_fence();
      issue_pv_chunk(ob, p, descV + (16384 >> 4));
      wg_wait<1>();
      fence_regs(oa);
      stage_o<0, 4>(oa, l0, l1, stg + lane_off);
      wg_fence();
      issue_pv_chunk(oc, p, descV + (32768 >> 4));
      if (wg == 0) bar_arrive(other_bar);
      tma_store_warp(&tmO, stg + (warp & 3) * 2048, 0, orow);
      wg_wait<1>();
      fence_regs(ob);
      stage_o<0, 4>(ob, l0, l1, stg + 8192 + lane_off);
      tma_store_warp(&tmO, stg + (warp & 3) * 2048 + 8192, 64, orow);
      wg_wait<0>();
      fence_regs(oc);
      stage_o<0, 4>(oc, l0, l1, stg + 16384 + lane_off);
      tma_store_warp(&tmO, stg + (warp & 3) * 2048 + 16384, 128, orow);
      asm volatile("cp.async.bulk.wait_group.read 0;" ::: "memory");
    }
  }
}

typedef CUresult (*EncodeTiledFn)(CUtensorMap*, CUtensorMapDataType, cuuint32_t, void*, const cuuint64_t*,
                                  const cuuint64_t*, const cuuint32_t*, const cuuint32_t*, CUtensorMapInterleave,
                                  CUtensorMapSwizzle, CUtensorMapL2promotion, CUtensorMapFloatOOBfill);

void make_map(EncodeTiledFn fn, CUtensorMap* m, const void* ptr, int box_rows) {
  cuuint64_t dims[2] = {(cuuint64_t)kD, (cuuint64_t)kH * kS};
  cuuint64_t strides[1] = {(cuuint64_t)kD * 2};
  cuuint32_t box[2] = {64, (cuuint32_t)box_rows};
  cuuint32_t es[2] = {1, 1};
  fn(m, CU_TENSOR_MAP_DATA_TYPE_BFLOAT16, 2, const_cast<void*>(ptr), dims, strides, box, es,
     CU_TENSOR_MAP_INTERLEAVE_NONE, CU_TENSOR_MAP_SWIZZLE_128B, CU_TENSOR_MAP_L2_PROMOTION_L2_128B,
     CU_TENSOR_MAP_FLOAT_OOB_FILL_NONE);
}

}

extern "C" void kernel_launch(void* const* d_in, const int* in_sizes, int n_in, void* d_out, int out_size) {
  static EncodeTiledFn encode = nullptr;
  if (!encode) {
    void* fn = nullptr;
    cudaDriverEntryPointQueryResult qres;
    cudaGetDriverEntryPoint("cuTensorMapEncodeTiled", &fn, cudaEnableDefault, &qres);
    encode = (EncodeTiledFn)fn;
    cudaFuncSetAttribute(attn_fwd_kernel, cudaFuncAttributeMaxDynamicSharedMemorySize, kSmemBytes);
  }
  CUtensorMap tmQ, tmK, tmV, tmO;
  make_map(encode, &tmQ, d_in[0], 64);
  make_map(encode, &tmK, d_in[1], 128);
  make_map(encode, &tmV, d_in[2], 128);
  make_map(encode, &tmO, d_out, 16);
  attn_fwd_kernel<<<kNumCtas, 384, kSmemBytes>>>(tmQ, tmK, tmV, tmO, (const __nv_bfloat16*)d_in[0]);
}
```
